```python
import torch

def _softmax(x, axis=-1):
    return torch.softmax(x, dim=axis)
def _gelu(x):
    return torch.nn.functional.gelu(x, approximate="tanh")
def _silu(x):
    return torch.nn.functional.silu(x)
def _sigmoid(x):
    return torch.sigmoid(x)
def _layernorm(x, axis=-1, eps=1e-5):
    m = x.mean(dim=axis, keepdim=True)
    v = x.var(dim=axis, keepdim=True, unbiased=False)
    return (x - m) / torch.sqrt(v + eps)
def _scatter_add(tgt, idx, src, axis=0):
    return tgt.clone().index_add_(axis, idx, src)
def _segment_sum(src, seg, n):
    out = torch.zeros((n,) + src.shape[1:], dtype=src.dtype)
    return out.index_add_(0, seg, src)
def _pad(x, pw):
    flat = tuple(v for pair in reversed(pw) for v in pair)
    return torch.nn.functional.pad(x, flat)

kernel_name = 'concat_heads__linear_kernel_hedgehog__ssm_conv_s4__prompt'

def setup_inputs():

    _w = (lambda a: (lambda t: t.to(torch.bfloat16) if t.is_floating_point() else t)(torch.as_tensor(a)))
    def _A_setup():
        B, S, D, H = 1, 2048, 640, 32
        Dh = D // H
        return {
            "x": _w((lambda *s: torch.randn(*s, dtype=torch.bfloat16) * 0.4)(B, S, D)),
            "wqkv": _w((lambda *s: torch.randn(*s, dtype=torch.bfloat16) * 0.4)(D, 3 * D)),
            "w_phi": _w((lambda *s: torch.randn(*s, dtype=torch.bfloat16) * 0.4)(H, Dh, Dh) * (Dh ** -0.5)),
            "wo": _w((lambda *s: torch.randn(*s, dtype=torch.bfloat16) * 0.05)(D, D)),
        }
    _A_in = _A_setup()

    def _B_setup():
        B, L, D, N = 1, 2048, 640, 128
        A_re = -(lambda _x: torch.exp(torch.as_tensor(_x)))((lambda *s: torch.randn(*s, dtype=torch.bfloat16) * 3.2)(D, N))
        A_im = torch.pi * (lambda *s: torch.randn(*s, dtype=torch.bfloat16) * 0.2)(D, N)
        B_re = (lambda *s: torch.randn(*s, dtype=torch.bfloat16) * 0.4)(D, N)
        B_im = (lambda *s: torch.randn(*s, dtype=torch.bfloat16) * 0.4)(D, N)
        C_re = (lambda *s: torch.randn(*s, dtype=torch.bfloat16) * 0.4)(D, N)
        C_im = (lambda *s: torch.randn(*s, dtype=torch.bfloat16) * 0.4)(D, N)
        log_dt = (lambda *s: torch.randn(*s, dtype=torch.bfloat16) * 0.2)(D) * 0.5 - 4.0
        Dskip = (lambda *s: torch.randn(*s, dtype=torch.bfloat16) * 0.4)(D)
        return {
            "u": _w((lambda *s: torch.randn(*s, dtype=torch.bfloat16) * 0.05)(B, L, D)),
            "A_re": _w(A_re),
            "A_im": _w(A_im),
            "B_re": _w(B_re),
            "B_im": _w(B_im),
            "C_re": _w(C_re),
            "C_im": _w(C_im),
            "log_dt": _w(log_dt),
            "Dskip": _w(Dskip),
        }
    _B_in = _B_setup()

    return {
        "A_x": _A_in["x"],
        "A_wqkv": _A_in["wqkv"],
        "A_w_phi": _A_in["w_phi"],
        "A_wo": _A_in["wo"],
        "B_u": _B_in["u"],
        "B_A_re": _B_in["A_re"],
        "B_A_im": _B_in["A_im"],
        "B_B_re": _B_in["B_re"],
        "B_B_im": _B_in["B_im"],
        "B_C_re": _B_in["C_re"],
        "B_C_im": _B_in["C_im"],
        "B_log_dt": _B_in["log_dt"],
        "B_Dskip": _B_in["Dskip"],
    }

def reference(A_x, A_wqkv, A_w_phi, A_wo, B_u, B_A_re, B_A_im, B_B_re, B_B_im, B_C_re, B_C_im, B_log_dt, B_Dskip):
    def _A_ref(x, wqkv, w_phi, wo):
        B, S, D = x.shape
        H = 32; Dh = D // H
        qkv = (lambda x, *d: x.permute(*d))((x @ wqkv).reshape(B, S, 3, H, Dh), 2, 0, 3, 1, 4)
        q, k, v = qkv[0], qkv[1], qkv[2]
        pq = torch.einsum("bhsd,hdf->bhsf", q, w_phi)
        pk = torch.einsum("bhsd,hdf->bhsf", k, w_phi)
        phi_q = torch.concatenate([_softmax(pq, axis=-1), _softmax(-pq, axis=-1)], axis=-1)
        phi_k = torch.concatenate([_softmax(pk, axis=-1), _softmax(-pk, axis=-1)], axis=-1)
        kv = torch.einsum("bhsf,bhsd->bhfd", phi_k, v)
        z  = torch.einsum("bhsf->bhf", phi_k)
        num = torch.einsum("bhqf,bhfd->bhqd", phi_q, kv)
        den = torch.einsum("bhqf,bhf->bhq", phi_q, z)[..., None] + 1e-6
        o = num / den
        return (lambda x, *d: x.permute(*d))(o, 0, 2, 1, 3).reshape(B, S, D) @ wo

    def _B_ref(u, A_re, A_im, B_re, B_im, C_re, C_im, log_dt, Dskip):
        Bsz, L, D = u.shape
        dt = torch.exp(log_dt)[:, None]
        A = A_re + 1j * A_im
        Bc = B_re + 1j * B_im
        Cc = C_re + 1j * C_im
        logdA = dt * A
        dB = dt * Bc
        l = (lambda x, dt: x.to(dt))(torch.arange(L), A_re.dtype)
        P = torch.exp(logdA[:, :, None] * l[None, None, :])
        K = torch.einsum("dn,dnl,dn->dl", Cc, P, dB).real
        L2 = 2 * L
        Kp = _pad(K, ((0, 0), (0, L)))
        up = (lambda x, *d: x.permute(*d))(u, 0, 2, 1)
        up = _pad(up, ((0, 0), (0, 0), (0, L)))
        Kf = (lambda x, axes=(-2,-1): torch.fft.rfft2(x.float(), dim=axes))(Kp[:, None, :], axes=(-2, -1))
        Uf = (lambda x, axes=(-2,-1): torch.fft.rfft2(x.float(), dim=axes))(up[:, :, None, :], axes=(-2, -1))
        Yf = Uf * Kf[None, :, :, :]
        y = (lambda x, s, axes=(-2,-1): torch.fft.irfft2(x, s=s, dim=axes).to(torch.bfloat16))(Yf, (1, L2), axes=(-2, -1))[:, :, 0, :L]
        y = (lambda x, *d: x.permute(*d))(y, 0, 2, 1) + u * Dskip[None, None, :]
        return y

    a = _A_ref(A_x, A_wqkv, A_w_phi, A_wo)
    b = _B_ref(B_u, B_A_re, B_A_im, B_B_re, B_B_im, B_C_re, B_C_im, B_log_dt, B_Dskip)
    return torch.concatenate([a, b], axis=-1)
```

```cpp
#include <cuda_runtime.h>
#include <cuda_bf16.h>
#include <cuda.h>
#include <stdint.h>

namespace {

constexpr int NCTA = 128;
constexpr int NTHREADS = 512;

constexpr uint32_t STAGE_BYTES = 47104;
constexpr uint32_t ST_WM = 16384, ST_WR = 40960;
constexpr uint32_t OFF_PHIK = 0;
constexpr uint32_t PHIK_UNIT = 2080;
constexpr uint32_t OFF_V = 41600;
constexpr uint32_t OFF_KVP = 0;
constexpr uint32_t KVP_BYTES = 14256;
constexpr uint32_t OFF_OUTST = 0;
constexpr uint32_t OFF_KVB = 20480;
constexpr uint32_t WO_BYTES = 12800;
constexpr uint32_t OFF_WO = 64256, OFF_WO6 = 51200;
constexpr uint32_t OFF_PAR = 141312;
constexpr uint32_t OFF_WPHI = 151040;
constexpr uint32_t OFF_WORK = 163840;
constexpr uint32_t WK_F = 16384, WK_USM = 14336, WK_XCH = 23040;
constexpr uint32_t OFF_USM = 192512;
constexpr uint32_t USM_PLANE = 2176, USM_CH = 4352, USM_PAD = 128;
constexpr uint32_t OFF_KC = 205568;
constexpr uint32_t KC_COPY = 2240, KC_CH = 4480;
constexpr uint32_t OFF_KT = 227968;
constexpr uint32_t KT_COPY = 192, KT_SET = 352, KT_CH = 704;
constexpr uint32_t OFF_BAR = 231488;
constexpr uint32_t OFF_MISC = OFF_BAR + 256;
constexpr uint32_t SMEM_BYTES = OFF_MISC + 272;

enum Bar : uint32_t {
    B_FULL = 0, B_EMPTY = 3, B_WO = 6, B_WOL = 7, B_KVD = 8, B_KVP = 9, B_KVGO = 10, B_UTILE = 11, B_GATE = 12,
    B_CNT = 13, B_WPHI = 15, B_PQ = 16, B_UDONE = 17, B_USM = 18, B_CONV = 20, B_PAR = 23
};

__device__ __align__(128) unsigned g_cnt_kv[8 * 32];
__device__ __align__(128) unsigned g_cnt_u[8 * 32];
__device__ __align__(128) float g_kvsum[2 * 8 * (KVP_BYTES / 4)];
constexpr int XBUF = 16 * 8 * 5 * 256;
__device__ __align__(128) unsigned g_hint_o[16 * 8 * 8];
__device__ __align__(128) unsigned g_hint_y[8 * 32];
__device__ __align__(128) uint4 g_o[XBUF];
__device__ __align__(128) uint4 g_ut[640 * 256];
__device__ __align__(128) uint4 g_yt[XBUF];
#define PROF(slot) do {} while (0)
#define PROF_IF(cond, slot) do {} while (0)
#define PROF_GT(cond, slot) do {} while (0)
#define PROF_EXIT() do {} while (0)
#define PROF_SMEM 0

__device__ __forceinline__ uint32_t smem_u32(const void* p) { return (uint32_t)__cvta_generic_to_shared(p); }
__device__ __forceinline__ void mbar_init(uint32_t bar, uint32_t cnt) {
    asm volatile("mbarrier.init.shared::cta.b64 [%0], %1;" ::"r"(bar), "r"(cnt) : "memory");
}
__device__ __forceinline__ void mbar_expect_tx(uint32_t bar, uint32_t bytes) {
    asm volatile("mbarrier.arrive.expect_tx.shared::cta.b64 _, [%0], %1;" ::"r"(bar), "r"(bytes) : "memory");
}
__device__ __forceinline__ void mbar_arrive(uint32_t bar) {
    asm volatile("mbarrier.arrive.shared::cta.b64 _, [%0];" ::"r"(bar) : "memory");
}
__device__ __forceinline__ void mbar_wait(uint32_t bar, uint32_t parity) {
    asm volatile("{\n"
                 ".reg .pred p, q;\n"
                 ".reg .u32 c;\n"
                 "mov.u32 c, 0;\n"
                 "WAIT_LOOP:\n"
                 "mbarrier.try_wait.parity.shared::cta.b64 p, [%0], %1;\n"
                 "add.u32 c, c, 1;\n"
                 "setp.lt.and.u32 q, c, 0x100000, !p;\n"
                 "@q bra WAIT_LOOP;\n"
                 "}" ::"r"(bar), "r"(parity) : "memory");
}
__device__ __forceinline__ void mbar_wait_long(uint32_t bar, uint32_t parity) {
    asm volatile("{\n"
                 ".reg .pred p, q;\n"
                 ".reg .u32 c;\n"
                 "mov.u32 c, 0;\n"
                 "WAIT_LOOP:\n"
                 "mbarrier.try_wait.parity.shared::cta.b64 p, [%0], %1, 5000;\n"
                 "add.u32 c, c, 1;\n"
                 "setp.lt.and.u32 q, c, 0x40000, !p;\n"
                 "@q bra WAIT_LOOP;\n"
                 "}" ::"r"(bar), "r"(parity) : "memory");
}
__device__ __forceinline__ void bar_sync(int id, int n) { asm volatile("bar.sync %0, %1;" ::"r"(id), "r"(n) : "memory"); }
__device__ __forceinline__ void fence_async_smem() { asm volatile("fence.proxy.async.shared::cta;" ::: "memory"); }
__device__ __forceinline__ void fence_async_global() { asm volatile("fence.proxy.async.global;" ::: "memory"); }
__device__ __forceinline__ void fence_gpu() { asm volatile("fence.acq_rel.gpu;" ::: "memory"); }
__device__ __forceinline__ unsigned ld_relaxed(const unsigned* p) {
    unsigned v;
    asm volatile("ld.relaxed.gpu.global.u32 %0, [%1];" : "=r"(v) : "l"(p) : "memory");
    return v;
}
__device__ __forceinline__ void ldg128_cg(uint32_t* r, const uint4* p) {
    asm volatile("ld.relaxed.gpu.global.v4.u32 {%0, %1, %2, %3}, [%4];" : "=r"(r[0]), "=r"(r[1]), "=r"(r[2]), "=r"(r[3]) : "l"(p) : "memory");
}
__device__ __forceinline__ unsigned ld_acquire(const unsigned* p) {
    unsigned v;
    asm volatile("ld.acquire.gpu.global.u32 %0, [%1];" : "=r"(v) : "l"(p) : "memory");
    return v;
}
__device__ __forceinline__ void red_inc(unsigned* p) { asm volatile("red.relaxed.gpu.global.add.u32 [%0], 1;" ::"l"(p) : "memory"); }
__device__ __forceinline__ void st_relaxed(unsigned* p, unsigned v) {
    asm volatile("st.relaxed.gpu.global.u32 [%0], %1;" ::"l"(p), "r"(v) : "memory");
}
__device__ __forceinline__ uint32_t tag_mismatch(const uint32_t* r, uint32_t tag) {
    uint32_t d;
    asm("{ .reg .b32 x, y; lop3.b32 x, %1, %2, %6, 0x7E; lop3.b32 y, %3, %4, %6, 0x7E; xor.b32 %0, %5, %6;\n"
        "lop3.b32 %0, %0, x, y, 0xFE; }"
        : "=r"(d) : "r"(r[0]), "r"(r[4]), "r"(r[8]), "r"(r[12]), "r"(r[16]), "r"(tag));
    return d;
}
__device__ __forceinline__ void wait_counter(const unsigned* p, unsigned target) {
    int it = 0;
    while ((int)(ld_relaxed(p) - target) < 0 && ++it < (1 << 20)) {}
    ld_acquire(p);
}
__device__ __forceinline__ void tma_load_2d(uint32_t dst, const CUtensorMap* m, uint32_t bar, int c0, int c1) {
    asm volatile("cp.async.bulk.tensor.2d.shared::cluster.global.mbarrier::complete_tx::bytes [%0], [%1, {%3, %4}], [%2];"
                 ::"r"(dst), "l"(m), "r"(bar), "r"(c0), "r"(c1) : "memory");
}
__device__ __forceinline__ void tma_load_3d(uint32_t dst, const CUtensorMap* m, uint32_t bar, int c0, int c1, int c2) {
    asm volatile("cp.async.bulk.tensor.3d.shared::cluster.global.mbarrier::complete_tx::bytes [%0], [%1, {%3, %4, %5}], [%2];"
                 ::"r"(dst), "l"(m), "r"(bar), "r"(c0), "r"(c1), "r"(c2) : "memory");
}
__device__ __forceinline__ void tma_load_4d(uint32_t dst, const CUtensorMap* m, uint32_t bar, int c0, int c1, int c2, int c3) {
    asm volatile("cp.async.bulk.tensor.4d.shared::cluster.global.mbarrier::complete_tx::bytes [%0], [%1, {%3, %4, %5, %6}], [%2];"
                 ::"r"(dst), "l"(m), "r"(bar), "r"(c0), "r"(c1), "r"(c2), "r"(c3) : "memory");
}
__device__ __forceinline__ void tma_load_5d(uint32_t dst, const CUtensorMap* m, uint32_t bar, int c0, int c1, int c2, int c3, int c4) {
    asm volatile("cp.async.bulk.tensor.5d.shared::cluster.global.mbarrier::complete_tx::bytes [%0], [%1, {%3, %4, %5, %6, %7}], [%2];"
                 ::"r"(dst), "l"(m), "r"(bar), "r"(c0), "r"(c1), "r"(c2), "r"(c3), "r"(c4) : "memory");
}
__device__ __forceinline__ void tma_store_2d(const CUtensorMap* m, uint32_t src, int c0, int c1) {
    asm volatile("cp.async.bulk.tensor.2d.global.shared::cta.bulk_group [%0, {%2, %3}], [%1];"
                 ::"l"(m), "r"(src), "r"(c0), "r"(c1) : "memory");
}
__device__ __forceinline__ void bulk_load(uint32_t dst, const void* src, uint32_t bytes, uint32_t bar) {
    asm volatile("cp.async.bulk.shared::cluster.global.mbarrier::complete_tx::bytes [%0], [%1], %2, [%3];"
                 ::"r"(dst), "l"(src), "r"(bytes), "r"(bar) : "memory");
}
__device__ __forceinline__ void cp_async16(uint32_t dst, const void* src) {
    asm volatile("cp.async.cg.shared.global [%0], [%1], 16;" ::"r"(dst), "l"(src) : "memory");
}
__device__ __forceinline__ void bulk_store(void* dst, uint32_t src, uint32_t bytes) {
    asm volatile("cp.async.bulk.global.shared::cta.bulk_group [%0], [%1], %2;" ::"l"(dst), "r"(src), "r"(bytes) : "memory");
}
__device__ __forceinline__ void bulk_reduce_f32(void* dst, uint32_t src, uint32_t bytes) {
    asm volatile("cp.reduce.async.bulk.global.shared::cta.bulk_group.add.f32 [%0], [%1], %2;" ::"l"(dst), "r"(src), "r"(bytes) : "memory");
}
__device__ __forceinline__ void bulk_commit() { asm volatile("cp.async.bulk.commit_group;" ::: "memory"); }
__device__ __forceinline__ void bulk_wait_all() { asm volatile("cp.async.bulk.wait_group 0;" ::: "memory"); }
__device__ __forceinline__ void bulk_wait_read() { asm volatile("cp.async.bulk.wait_group.read 0;" ::: "memory"); }
__device__ __forceinline__ void prefetch_map(const CUtensorMap* m) { asm volatile("prefetch.tensormap [%0];" ::"l"(m) : "memory"); }

__device__ __forceinline__ void wg_fence() { asm volatile("wgmma.fence.sync.aligned;" ::: "memory"); }
__device__ __forceinline__ void wg_commit() { asm volatile("wgmma.commit_group.sync.aligned;" ::: "memory"); }
template <int N> __device__ __forceinline__ void wg_wait() { asm volatile("wgmma.wait_group.sync.aligned %0;" ::"n"(N) : "memory"); }
template <int N> __device__ __forceinline__ void pin_regs(float* d) {
#pragma unroll
    for (int i = 0; i < N; i++) asm volatile("" : "+f"(d[i])::"memory");
}
__device__ __forceinline__ uint64_t make_desc(uint32_t addr, uint32_t lbo, uint32_t sbo, uint32_t mode) {
    return (uint64_t)(((addr & 0x3FFFF) >> 4) | ((lbo >> 4) << 16)) | ((uint64_t)((sbo >> 4) | (mode << 30)) << 32);
}
__device__ __forceinline__ uint32_t pack_bf16(float lo, float hi) {
    uint32_t r;
    asm("cvt.rn.bf16x2.f32 %0, %1, %2;" : "=r"(r) : "f"(hi), "f"(lo));
    return r;
}
__device__ __forceinline__ float ex2(float x) { float r; asm("ex2.approx.ftz.f32 %0, %1;" : "=f"(r) : "f"(x)); return r; }
__device__ __forceinline__ float rcp(float x) { float r; asm("rcp.approx.ftz.f32 %0, %1;" : "=f"(r) : "f"(x)); return r; }
__device__ __forceinline__ void sts128(uint32_t a, uint32_t x, uint32_t y, uint32_t z, uint32_t w) {
    asm volatile("st.shared.v4.b32 [%0], {%1, %2, %3, %4};" ::"r"(a), "r"(x), "r"(y), "r"(z), "r"(w) : "memory");
}
__device__ __forceinline__ void sts64(uint32_t a, uint32_t x, uint32_t y) {
    asm volatile("st.shared.v2.b32 [%0], {%1, %2};" ::"r"(a), "r"(x), "r"(y) : "memory");
}
__device__ __forceinline__ void sts32(uint32_t a, uint32_t x) { asm volatile("st.shared.b32 [%0], %1;" ::"r"(a), "r"(x) : "memory"); }
__device__ __forceinline__ void sts16(uint32_t a, uint32_t x) { asm volatile("st.shared.b16 [%0], %1;" ::"r"(a), "h"((uint16_t)x) : "memory"); }
__device__ __forceinline__ uint4 lds128(uint32_t a) {
    uint4 v;
    asm volatile("ld.shared.v4.b32 {%0, %1, %2, %3}, [%4];" : "=r"(v.x), "=r"(v.y), "=r"(v.z), "=r"(v.w) : "r"(a) : "memory");
    return v;
}
__device__ __forceinline__ uint2 lds64(uint32_t a) {
    uint2 v;
    asm volatile("ld.shared.v2.b32 {%0, %1}, [%2];" : "=r"(v.x), "=r"(v.y) : "r"(a) : "memory");
    return v;
}
__device__ __forceinline__ float lds_bf16(uint32_t a) {
    uint16_t v;
    asm volatile("ld.shared.b16 %0, [%1];" : "=h"(v) : "r"(a) : "memory");
    return __uint_as_float((uint32_t)v << 16);
}
__device__ __forceinline__ uint32_t lds32(uint32_t a) {
    uint32_t v;
    asm volatile("ld.shared.b32 %0, [%1];" : "=r"(v) : "r"(a) : "memory");
    return v;
}
__device__ __forceinline__ void ldsm4(uint32_t* r, uint32_t a) {
    asm volatile("ldmatrix.sync.aligned.m8n8.x4.shared.b16 {%0, %1, %2, %3}, [%4];"
                 : "=r"(r[0]), "=r"(r[1]), "=r"(r[2]), "=r"(r[3]) : "r"(a) : "memory");
}
__device__ __forceinline__ int fresh_lane() {
    int v;
    asm volatile("mov.u32 %0, %%laneid;" : "=r"(v));
    return v;
}
__device__ __forceinline__ bool elect_one() {
    uint32_t p;
    asm volatile("{ .reg .pred p; elect.sync _|p, 0xffffffff; selp.b32 %0, 1, 0, p; }" : "=r"(p));
    return p != 0;
}
__device__ __forceinline__ void ldsm4t(uint32_t* r, uint32_t a) {
    asm volatile("ldmatrix.sync.aligned.m8n8.x4.trans.shared.b16 {%0, %1, %2, %3}, [%4];"
                 : "=r"(r[0]), "=r"(r[1]), "=r"(r[2]), "=r"(r[3]) : "r"(a) : "memory");
}
__device__ __forceinline__ void ldsm2t(uint32_t* r, uint32_t a) {
    asm volatile("ldmatrix.sync.aligned.m8n8.x2.trans.shared.b16 {%0, %1}, [%2];" : "=r"(r[0]), "=r"(r[1]) : "r"(a) : "memory");
}
__device__ __forceinline__ void stsm4(uint32_t a, uint32_t x, uint32_t y, uint32_t z, uint32_t w) {
    asm volatile("stmatrix.sync.aligned.m8n8.x4.shared.b16 [%0], {%1, %2, %3, %4};" ::"r"(a), "r"(x), "r"(y), "r"(z), "r"(w) : "memory");
}
__device__ __forceinline__ void stsm4t(uint32_t a, uint32_t x, uint32_t y, uint32_t z, uint32_t w) {
    asm volatile("stmatrix.sync.aligned.m8n8.x4.trans.shared.b16 [%0], {%1, %2, %3, %4};" ::"r"(a), "r"(x), "r"(y), "r"(z), "r"(w) : "memory");
}

__device__ __forceinline__ void mma16816(float* c, uint32_t a0, uint32_t a1, uint32_t a2, uint32_t a3, uint32_t b0, uint32_t b1) {
    asm volatile("mma.sync.aligned.m16n8k16.row.col.f32.bf16.bf16.f32 {%0, %1, %2, %3}, {%4, %5, %6, %7}, {%8, %9}, {%0, %1, %2, %3};"
        : "+f"(c[0]), "+f"(c[1]), "+f"(c[2]), "+f"(c[3]) : "r"(a0), "r"(a1), "r"(a2), "r"(a3), "r"(b0), "r"(b1));
}

__device__ __forceinline__ void mma16816_f16(float* c, const uint32_t* a, uint32_t b0, uint32_t b1) {
    asm volatile("mma.sync.aligned.m16n8k16.row.col.f32.f16.f16.f32 {%0, %1, %2, %3}, {%4, %5, %6, %7}, {%8, %9}, {%0, %1, %2, %3};"
                 : "+f"(c[0]), "+f"(c[1]), "+f"(c[2]), "+f"(c[3]) : "r"(a[0]), "r"(a[1]), "r"(a[2]), "r"(a[3]), "r"(b0), "r"(b1));
}

template <int TA, int TB>
__device__ __forceinline__ void wgmma_ss_f16_n48(float* d, uint64_t da, uint64_t db, int acc) {
    asm volatile("{ .reg .pred p; setp.ne.b32 p, %26, 0; wgmma.mma_async.sync.aligned.m64n48k16.f32.f16.f16 "
        "{%0, %1, %2, %3, %4, %5, %6, %7, %8, %9, %10, %11, %12, %13, %14, %15, %16, %17, %18, %19, %20, %21, %22, %23}, "
        "%24, %25, p, 1, 1, %27, %28; }"
        :
        "+f"(d[0]), "+f"(d[1]), "+f"(d[2]), "+f"(d[3]), "+f"(d[4]), "+f"(d[5]), "+f"(d[6]), "+f"(d[7]), "+f"(d[8]), "+f"(d[9]), "+f"(d[10]), "+f"(d[11]),
        "+f"(d[12]), "+f"(d[13]), "+f"(d[14]), "+f"(d[15]), "+f"(d[16]), "+f"(d[17]), "+f"(d[18]), "+f"(d[19]), "+f"(d[20]), "+f"(d[21]), "+f"(d[22]),
        "+f"(d[23])
        : "l"(da), "l"(db), "r"(acc), "n"(TA), "n"(TB));
}
template <int TA, int TB>
__device__ __forceinline__ void wgmma_ss_n80(float* d, uint64_t da, uint64_t db, int acc) {
    asm volatile("{ .reg .pred p; setp.ne.b32 p, %42, 0; wgmma.mma_async.sync.aligned.m64n80k16.f32.bf16.bf16 "
        "{%0, %1, %2, %3, %4, %5, %6, %7, %8, %9, %10, %11, %12, %13, %14, %15, %16, %17, %18, %19, %20, %21, %22, %23, %24, %25, %26, %27, %28, %29, %30, %31, "
        "%32, %33, %34, %35, %36, %37, %38, %39}, "
        "%40, %41, p, 1, 1, %43, %44; }"
        :
        "+f"(d[0]), "+f"(d[1]), "+f"(d[2]), "+f"(d[3]), "+f"(d[4]), "+f"(d[5]), "+f"(d[6]), "+f"(d[7]), "+f"(d[8]), "+f"(d[9]), "+f"(d[10]), "+f"(d[11]),
        "+f"(d[12]), "+f"(d[13]), "+f"(d[14]), "+f"(d[15]), "+f"(d[16]), "+f"(d[17]), "+f"(d[18]), "+f"(d[19]), "+f"(d[20]), "+f"(d[21]), "+f"(d[22]),
        "+f"(d[23]), "+f"(d[24]), "+f"(d[25]), "+f"(d[26]), "+f"(d[27]), "+f"(d[28]), "+f"(d[29]), "+f"(d[30]), "+f"(d[31]), "+f"(d[32]), "+f"(d[33]),
        "+f"(d[34]), "+f"(d[35]), "+f"(d[36]), "+f"(d[37]), "+f"(d[38]), "+f"(d[39])
        : "l"(da), "l"(db), "r"(acc), "n"(TA), "n"(TB));
}
template <int TB>
__device__ __forceinline__ void wgmma_rs_n48(float* d, const uint32_t* a, uint64_t db, int acc) {
    asm volatile("{ .reg .pred p; setp.ne.b32 p, %29, 0; wgmma.mma_async.sync.aligned.m64n48k16.f32.bf16.bf16 "
        "{%0, %1, %2, %3, %4, %5, %6, %7, %8, %9, %10, %11, %12, %13, %14, %15, %16, %17, %18, %19, %20, %21, %22, %23}, "
        "{%24, %25, %26, %27}, %28, p, 1, 1, %30; }"
        :
        "+f"(d[0]), "+f"(d[1]), "+f"(d[2]), "+f"(d[3]), "+f"(d[4]), "+f"(d[5]), "+f"(d[6]), "+f"(d[7]), "+f"(d[8]), "+f"(d[9]), "+f"(d[10]), "+f"(d[11]),
        "+f"(d[12]), "+f"(d[13]), "+f"(d[14]), "+f"(d[15]), "+f"(d[16]), "+f"(d[17]), "+f"(d[18]), "+f"(d[19]), "+f"(d[20]), "+f"(d[21]), "+f"(d[22]),
        "+f"(d[23])
        : "r"(a[0]), "r"(a[1]), "r"(a[2]), "r"(a[3]), "l"(db), "r"(acc), "n"(TB));
}
template <int TB>
__device__ __forceinline__ void wgmma_rs_n80(float* d, const uint32_t* a, uint64_t db, int acc) {
    asm volatile("{ .reg .pred p; setp.ne.b32 p, %45, 0; wgmma.mma_async.sync.aligned.m64n80k16.f32.bf16.bf16 "
        "{%0, %1, %2, %3, %4, %5, %6, %7, %8, %9, %10, %11, %12, %13, %14, %15, %16, %17, %18, %19, %20, %21, %22, %23, %24, %25, %26, %27, %28, %29, %30, %31, "
        "%32, %33, %34, %35, %36, %37, %38, %39}, "
        "{%40, %41, %42, %43}, %44, p, 1, 1, %46; }"
        :
        "+f"(d[0]), "+f"(d[1]), "+f"(d[2]), "+f"(d[3]), "+f"(d[4]), "+f"(d[5]), "+f"(d[6]), "+f"(d[7]), "+f"(d[8]), "+f"(d[9]), "+f"(d[10]), "+f"(d[11]),
        "+f"(d[12]), "+f"(d[13]), "+f"(d[14]), "+f"(d[15]), "+f"(d[16]), "+f"(d[17]), "+f"(d[18]), "+f"(d[19]), "+f"(d[20]), "+f"(d[21]), "+f"(d[22]),
        "+f"(d[23]), "+f"(d[24]), "+f"(d[25]), "+f"(d[26]), "+f"(d[27]), "+f"(d[28]), "+f"(d[29]), "+f"(d[30]), "+f"(d[31]), "+f"(d[32]), "+f"(d[33]),
        "+f"(d[34]), "+f"(d[35]), "+f"(d[36]), "+f"(d[37]), "+f"(d[38]), "+f"(d[39])
        : "r"(a[0]), "r"(a[1]), "r"(a[2]), "r"(a[3]), "l"(db), "r"(acc), "n"(TB));
}
template <int TB>
__device__ __forceinline__ void wgmma_rs_n88(float* d, const uint32_t* a, uint64_t db, int acc) {
    asm volatile("{ .reg .pred p; setp.ne.b32 p, %49, 0; wgmma.mma_async.sync.aligned.m64n88k16.f32.bf16.bf16 "
        "{%0, %1, %2, %3, %4, %5, %6, %7, %8, %9, %10, %11, %12, %13, %14, %15, %16, %17, %18, %19, %20, %21, %22, %23, %24, %25, %26, %27, %28, %29, %30, %31, "
        "%32, %33, %34, %35, %36, %37, %38, %39, %40, %41, %42, %43}, "
        "{%44, %45, %46, %47}, %48, p, 1, 1, %50; }"
        :
        "+f"(d[0]), "+f"(d[1]), "+f"(d[2]), "+f"(d[3]), "+f"(d[4]), "+f"(d[5]), "+f"(d[6]), "+f"(d[7]), "+f"(d[8]), "+f"(d[9]), "+f"(d[10]), "+f"(d[11]),
        "+f"(d[12]), "+f"(d[13]), "+f"(d[14]), "+f"(d[15]), "+f"(d[16]), "+f"(d[17]), "+f"(d[18]), "+f"(d[19]), "+f"(d[20]), "+f"(d[21]), "+f"(d[22]),
        "+f"(d[23]), "+f"(d[24]), "+f"(d[25]), "+f"(d[26]), "+f"(d[27]), "+f"(d[28]), "+f"(d[29]), "+f"(d[30]), "+f"(d[31]), "+f"(d[32]), "+f"(d[33]),
        "+f"(d[34]), "+f"(d[35]), "+f"(d[36]), "+f"(d[37]), "+f"(d[38]), "+f"(d[39]), "+f"(d[40]), "+f"(d[41]), "+f"(d[42]), "+f"(d[43])
        : "r"(a[0]), "r"(a[1]), "r"(a[2]), "r"(a[3]), "l"(db), "r"(acc), "n"(TB));
}
template <int TB>
__device__ __forceinline__ void wgmma_rs_n192(float* d, const uint32_t* a, uint64_t db, int acc) {
    asm volatile("{ .reg .pred p; setp.ne.b32 p, %101, 0; wgmma.mma_async.sync.aligned.m64n192k16.f32.bf16.bf16 "
        "{%0, %1, %2, %3, %4, %5, %6, %7, %8, %9, %10, %11, %12, %13, %14, %15, %16, %17, %18, %19, %20, %21, %22, %23, %24, %25, %26, %27, %28, %29, %30, %31, "
        "%32, %33, %34, %35, %36, %37, %38, %39, %40, %41, %42, %43, %44, %45, %46, %47, %48, %49, %50, %51, %52, %53, %54, %55, %56, %57, %58, %59, %60, %61, "
        "%62, %63, %64, %65, %66, %67, %68, %69, %70, %71, %72, %73, %74, %75, %76, %77, %78, %79, %80, %81, %82, %83, %84, %85, %86, %87, %88, %89, %90, %91, "
        "%92, %93, %94, %95}, "
        "{%96, %97, %98, %99}, %100, p, 1, 1, %102; }"
        :
        "+f"(d[0]), "+f"(d[1]), "+f"(d[2]), "+f"(d[3]), "+f"(d[4]), "+f"(d[5]), "+f"(d[6]), "+f"(d[7]), "+f"(d[8]), "+f"(d[9]), "+f"(d[10]), "+f"(d[11]),
        "+f"(d[12]), "+f"(d[13]), "+f"(d[14]), "+f"(d[15]), "+f"(d[16]), "+f"(d[17]), "+f"(d[18]), "+f"(d[19]), "+f"(d[20]), "+f"(d[21]), "+f"(d[22]),
        "+f"(d[23]), "+f"(d[24]), "+f"(d[25]), "+f"(d[26]), "+f"(d[27]), "+f"(d[28]), "+f"(d[29]), "+f"(d[30]), "+f"(d[31]), "+f"(d[32]), "+f"(d[33]),
        "+f"(d[34]), "+f"(d[35]), "+f"(d[36]), "+f"(d[37]), "+f"(d[38]), "+f"(d[39]), "+f"(d[40]), "+f"(d[41]), "+f"(d[42]), "+f"(d[43]), "+f"(d[44]),
        "+f"(d[45]), "+f"(d[46]), "+f"(d[47]), "+f"(d[48]), "+f"(d[49]), "+f"(d[50]), "+f"(d[51]), "+f"(d[52]), "+f"(d[53]), "+f"(d[54]), "+f"(d[55]),
        "+f"(d[56]), "+f"(d[57]), "+f"(d[58]), "+f"(d[59]), "+f"(d[60]), "+f"(d[61]), "+f"(d[62]), "+f"(d[63]), "+f"(d[64]), "+f"(d[65]), "+f"(d[66]),
        "+f"(d[67]), "+f"(d[68]), "+f"(d[69]), "+f"(d[70]), "+f"(d[71]), "+f"(d[72]), "+f"(d[73]), "+f"(d[74]), "+f"(d[75]), "+f"(d[76]), "+f"(d[77]),
        "+f"(d[78]), "+f"(d[79]), "+f"(d[80]), "+f"(d[81]), "+f"(d[82]), "+f"(d[83]), "+f"(d[84]), "+f"(d[85]), "+f"(d[86]), "+f"(d[87]), "+f"(d[88]),
        "+f"(d[89]), "+f"(d[90]), "+f"(d[91]), "+f"(d[92]), "+f"(d[93]), "+f"(d[94]), "+f"(d[95])
        : "r"(a[0]), "r"(a[1]), "r"(a[2]), "r"(a[3]), "l"(db), "r"(acc), "n"(TB));
}

#define PROFC(k) PROF_IF(t == 0 && (c == 1 || c == 3), 64 + (c == 3 ? 8 : 0) + (k))
#define UUNR 2
#define UPOS 2
constexpr int kUUnroll = UUNR;
struct Params {
    const __nv_bfloat16* ssm[8];
    const __nv_bfloat16* w_phi;
    __nv_bfloat16* out;
};

template <bool NORM>
__device__ __forceinline__ void dual_softmax(const float* pin, uint32_t* w) {
    constexpr float L2E = 1.4426950408889634f;
    float p[40];
    uint32_t pmax, pmin;
#pragma unroll
    for (int t = 0; t < 10; t++) {
        const uint32_t r = pack_bf16(pin[4 * t], pin[4 * t + 1]);
        p[4 * t] = __uint_as_float(r << 16);
        p[4 * t + 1] = __uint_as_float(r & 0xFFFF0000u);
        if (t == 0) {
            pmax = pmin = r;
        } else {
            asm("max.bf16x2 %0, %0, %1;" : "+r"(pmax) : "r"(r));
            asm("min.bf16x2 %0, %0, %1;" : "+r"(pmin) : "r"(r));
        }
    }
    const float mx = fmaxf(__uint_as_float(pmax << 16), __uint_as_float(pmax & 0xFFFF0000u));
    const float mn = fminf(__uint_as_float(pmin << 16), __uint_as_float(pmin & 0xFFFF0000u));
    const float mxs = -mx * L2E, mns = mn * L2E;
    float e[20];
    float s0 = 0.f, s1 = 0.f;
#pragma unroll
    for (int t = 0; t < 10; t++) {
        e[2 * t] = ex2(fmaf(p[4 * t], L2E, mxs));
        e[2 * t + 1] = ex2(fmaf(p[4 * t + 1], L2E, mxs));
        s0 += e[2 * t];
        s1 += e[2 * t + 1];
    }
    float inv = NORM ? rcp(s0 + s1) : 1.f;
#pragma unroll
    for (int t = 0; t < 10; t++) w[t] = pack_bf16(e[2 * t] * inv, e[2 * t + 1] * inv);
    s0 = 0.f;
    s1 = 0.f;
#pragma unroll
    for (int t = 0; t < 10; t++) {
        e[2 * t] = ex2(fmaf(p[4 * t], -L2E, mns));
        e[2 * t + 1] = ex2(fmaf(p[4 * t + 1], -L2E, mns));
        s0 += e[2 * t];
        s1 += e[2 * t + 1];
    }
    inv = NORM ? rcp(s0 + s1) : 1.f;
#pragma unroll
    for (int t = 0; t < 10; t++) w[10 + t] = pack_bf16(e[2 * t] * inv, e[2 * t + 1] * inv);
}

__device__ __forceinline__ uint32_t pack_f16(float lo, float hi) {
    uint32_t r;
    asm("cvt.rn.f16x2.f32 %0, %1, %2;" : "=r"(r) : "f"(hi), "f"(lo));
    return r;
}
struct cplx2h { uint32_t r, i; };
__device__ __forceinline__ cplx2h hmul(cplx2h a, uint32_t m) {
    cplx2h o;
    asm("{ .reg .b16 l, h; .reg .b32 r2, i2, t, n; mov.b32 {l, h}, %4; mov.b32 r2, {l, l}; mov.b32 i2, {h, h};\n"
        "mul.rn.f16x2 t, %2, r2; neg.f16x2 n, %3; fma.rn.f16x2 %0, n, i2, t;\n"
        "mul.rn.f16x2 t, %2, i2; fma.rn.f16x2 %1, %3, r2, t; }"
        : "=r"(o.r), "=r"(o.i) : "r"(a.r), "r"(a.i), "r"(m));
    return o;
}
__device__ __forceinline__ cplx2h lows(cplx2h a, cplx2h b) { return {__byte_perm(a.r, b.r, 0x5410), __byte_perm(a.i, b.i, 0x5410)}; }

struct cplx { float r, i; };
__device__ __forceinline__ cplx cmul(cplx a, cplx b) {
    return {fmaf(a.r, b.r, -a.i * b.i), fmaf(a.r, b.i, a.i * b.r)};
}
__device__ __forceinline__ cplx cmul_conj(cplx a, cplx b) {
    return {fmaf(a.r, b.r, -a.i * b.i), fmaf(-a.r, b.i, -a.i * b.r)};
}
__device__ __forceinline__ cplx cexp_small(float a2, float omega, float l) {
    const float th = omega * l, m = ex2(a2 * l);
    return {m * __cosf(th), m * __sinf(th)};
}
__device__ __forceinline__ cplx cexp_reduced(float a2, float rh, float rl, float l) {
    const float x = rh * l;
    const float th = fmaf(rl, l, x - rintf(x)) * 6.283185307179586f, m = ex2(a2 * l);
    return {m * __cosf(th), m * __sinf(th)};
}

__device__ __forceinline__ uint32_t band_word(int v, int lo, int hi) {
    return ((v >= lo && v <= hi) ? 0x3F80u : 0u) | ((v + 1 >= lo && v + 1 <= hi) ? 0x3F800000u : 0u);
}

__global__ void __launch_bounds__(NTHREADS, 1)
fused_kernel(const __grid_constant__ CUtensorMap map_x, const __grid_constant__ CUtensorMap map_wm,
             const __grid_constant__ CUtensorMap map_wr, const __grid_constant__ CUtensorMap map_wo,
             const __grid_constant__ CUtensorMap map_u, const __grid_constant__ CUtensorMap map_ur,
             const __grid_constant__ CUtensorMap map_out, const __grid_constant__ Params prm) {
    extern __shared__ __align__(1024) uint8_t smem_raw[];
    const uint32_t sb = smem_u32(smem_raw);
    const uint32_t bars = sb + OFF_BAR;
    auto bar = [&](uint32_t i) { return bars + 8 * i; };
    const int tid = threadIdx.x;
    const int warp = __shfl_sync(0xffffffffu, tid >> 5, 0);
    const int lane = tid & 31;
    const int g = lane >> 2, q = lane & 3;
    const int b = blockIdx.x;
    const int ti = ((b >> 5) << 2) + (b & 3);
    const int tj = (((b >> 3) & 3) << 1) + ((b >> 2) & 1);
    const int cg = b >> 4, tb = b & 15;

    if ((warp >> 2) == 2 && elect_one()) {
        const int w = warp & 3;
        const uint32_t bytes = w < 3 ? 1280 : (b == NCTA - 1 ? 16 : 32), off = w < 3 ? b * 1280 : (10 * b) & ~15;
        const uint32_t dst = w < 3 ? sb + OFF_PAR + w * 2560 : sb + OFF_MISC + 64;
        mbar_init(bar(B_PAR + w), 1);
        mbar_expect_tx(bar(B_PAR + w), 2 * bytes);
        bulk_load(dst, reinterpret_cast<const char*>(prm.ssm[2 * w]) + off, bytes, bar(B_PAR + w));
        bulk_load(dst + (w < 3 ? 1280 : 32), reinterpret_cast<const char*>(prm.ssm[2 * w + 1]) + off, bytes, bar(B_PAR + w));
        PROF_IF(w == 0, 39);
    }
    if (warp == 0) {
        if (elect_one()) {
#pragma unroll
            for (int s = 0; s < 3; s++) mbar_init(bar(B_FULL + s), 1);
        }
        __syncwarp();
        asm volatile("bar.arrive 0, %0;" ::"r"(NTHREADS) : "memory");
        if (elect_one()) {
            mbar_expect_tx(bar(B_FULL), STAGE_BYTES);
            tma_load_2d(sb, &map_x, bar(B_FULL), 0, ti * 128);
            tma_load_3d(sb + ST_WM, &map_wm, bar(B_FULL), tj * 80, 0, 0);
            tma_load_3d(sb + ST_WR, &map_wr, bar(B_FULL), tj * 80 + 64, 0, 0);
            PROF(51);
        }
    }

    if (warp < 8) {
        if (warp == 0) bar_sync(5, 128); else bar_sync(0, NTHREADS);
        asm volatile("setmaxnreg.inc.sync.aligned.u32 168;");
        const int wg = warp >> 2, wq = warp & 3;
        unsigned* const ohint = g_hint_o + (ti * 8 + warp) * 8;
        PROF_IF(tid == 0, 53);
        {
#pragma unroll
            for (int u = 0; u < 4; u++)
                if (u < 3 || tid < 32) sts128(sb + OFF_WPHI + (tid + 256 * u) * 16, 0, 0, 0, 0);
            bar_sync(1, 256);
            const uint32_t* wsrc = reinterpret_cast<const uint32_t*>(prm.w_phi) + tj * 800;
#pragma unroll
            for (int u = 0; u < 4; u++) {
                const int idx = tid + 256 * u, c = idx / 10;
                if (u < 3 || tid < 32)
                    asm volatile("cp.async.ca.shared.global [%0], [%1], 4;" ::"r"(sb + OFF_WPHI + (idx - c * 10) * 1280 + c * 16 + 4 * (c / 20)),
                                 "l"(wsrc + idx) : "memory");
            }
        }
        float am[96], ar[24];
        {
            const uint32_t arow = sb + (warp * 16 + (lane & 15)) * 128;
            const uint32_t ax = (((lane >> 4) ^ lane) & 7) << 4;
            const uint64_t dM = make_desc(sb + ST_WM, 8192, 1024, 1);
            const uint64_t dR = make_desc(sb + ST_WR, 2048, 256, 3);
            const uint32_t a0 = arow + ax, a1 = arow + (ax ^ 32), a2 = arow + (ax ^ 64), a3 = arow + (ax ^ 96);
            uint32_t so = 0, fb = bar(B_FULL), eb = bar(B_EMPTY + 2), ph = 0;
#pragma unroll 1
            for (int kb = 0; kb < 10; kb++) {
                mbar_wait(fb, ph);
                PROF_IF(tid == 0 && kb == 0, 0); PROF_GT(tid == 0 && kb == 0, 0);
                const uint64_t sd = so >> 4;
                uint32_t f0[8], f1[8];
                ldsm4(f0, a0 + so);
                ldsm4(f0 + 4, a1 + so);
                wg_fence();
                wgmma_rs_n192<1>(am, f0, dM + sd, kb != 0);
                wgmma_rs_n48<1>(ar, f0, dR + sd, kb != 0);
                wgmma_rs_n192<1>(am, f0 + 4, dM + sd + 128, 1);
                wgmma_rs_n48<1>(ar, f0 + 4, dR + sd + 32, 1);
                wg_commit();
                wg_wait<1>();
                if (kb != 0 && elect_one()) mbar_arrive(eb);
                ldsm4(f1, a2 + so);
                ldsm4(f1 + 4, a3 + so);
                wg_fence();
                wgmma_rs_n192<1>(am, f1, dM + sd + 256, 1);
                wgmma_rs_n48<1>(ar, f1, dR + sd + 64, 1);
                wgmma_rs_n192<1>(am, f1 + 4, dM + sd + 384, 1);
                wgmma_rs_n48<1>(ar, f1 + 4, dR + sd + 96, 1);
                wg_commit();
                eb = fb + 8 * (B_EMPTY - B_FULL);
                so += STAGE_BYTES;
                fb += 8;
                if (so == 3 * STAGE_BYTES) { so = 0; fb = bar(B_FULL); ph ^= 1; }
                wg_wait<1>();
            }
            wg_wait<0>();
            pin_regs<96>(am);
            pin_regs<24>(ar);
        }
        if (lane == 0) mbar_arrive(bar(B_GATE));
        PROF_IF(tid == 0, 1); PROF_GT(tid == 0, 1);
        asm volatile("cp.async.wait_all;" ::: "memory");
        fence_async_smem();
        bar_sync(1, 256);

        float pk[40];
        uint32_t qf[20];
        const uint64_t dP = make_desc(sb + OFF_WPHI, 128, 1280, 0);
        {
            const uint32_t vaddr = sb + OFF_V + (warp * 16 + (lane & 15)) * 16;
#pragma unroll
            for (int t = 0; t < 10; t += 2) {
                const float* s0 = t < 8 ? am + 64 + 4 * t : ar + 16 + 4 * (t - 8);
                const int un = t + (lane >> 4);
                stsm4(vaddr + (un + (un >= 5)) * 2048, pack_bf16(s0[0], s0[1]), pack_bf16(s0[2], s0[3]), pack_bf16(s0[4], s0[5]),
                      pack_bf16(s0[6], s0[7]));
            }
            if (lane < 16) sts128(vaddr + 5 * 2048, 0x3F803F80u, 0x3F803F80u, 0x3F803F80u, 0x3F803F80u);
            uint32_t kf[20];
#pragma unroll
            for (int t = 0; t < 10; t++) {
                const float* sk = t < 8 ? am + 32 + 4 * t : ar + 8 + 4 * (t - 8);
                kf[2 * t] = pack_bf16(sk[0], sk[1]);
                kf[2 * t + 1] = pack_bf16(sk[2], sk[3]);
            }
            wg_fence();
#pragma unroll
            for (int kc = 0; kc < 5; kc++) wgmma_rs_n80<1>(pk, kf + 4 * kc, dP + kc * 16, kc != 0);
            wg_commit();
#pragma unroll
            for (int t = 0; t < 10; t++) {
                const float* sq = t < 8 ? am + 4 * t : ar + 4 * (t - 8);
                qf[2 * t] = pack_bf16(sq[0], sq[1]);
                qf[2 * t + 1] = pack_bf16(sq[2], sq[3]);
            }
            wg_wait<0>();
            pin_regs<40>(pk);
        }
        PROF_IF(tid == 0, 2);
#pragma unroll
        for (int r = 0; r < 2; r++) {
            uint32_t w[20];
            dual_softmax<true>(pk + 2 * r, w);
            const uint32_t a = sb + OFF_PHIK + 5 * q * PHIK_UNIT + (warp * 16 + g + 8 * r) * 16;
#pragma unroll
            for (int u = 0; u < 5; u++) sts128(a + u * PHIK_UNIT, w[4 * u], w[4 * u + 1], w[4 * u + 2], w[4 * u + 3]);
        }
        PROF_IF(tid == 0, 3);
        fence_async_smem();
        bar_sync(1, 256);
        {
            float kv[40];
            const uint64_t dV = make_desc(sb + OFF_V + wg * 5 * 2048, 128, 2048, 0);
            const uint64_t dF = make_desc(sb + OFF_PHIK + wg * 10 * PHIK_UNIT, 128, PHIK_UNIT, 0);
            wg_fence();
#pragma unroll
            for (int ks = 0; ks < 8; ks++) wgmma_ss_n80<1, 1>(kv, dV + ks * 16, dF + ks * 16, ks != 0);
            wg_commit();
            wg_wait<0>();
            pin_regs<40>(kv);
            bar_sync(1, 256);
            if (tid == 0) mbar_arrive(bar(B_KVD));
#pragma unroll
            for (int r = 0; r < 2; r++) {
                const int m = wq * 16 + g + 8 * r - 8 * wg;
                const bool isv = m >= 0 && m < 40, isz = m == (wg ? -8 : 40);
                const int hl = m >= 20, d = isz ? 20 : m - 20 * hl;
                const uint32_t a = sb + OFF_KVP + ((d >> 1) * 162 + 8 * q + 4 * wg + (d & 1)) * 8;
#pragma unroll
                for (int T = 0; T < 10; T++)
                    if (isz || (isv && hl == T / 5))
                        sts64(a + ((T % 5) * 32 + (T / 5) * 2) * 8, __float_as_uint(kv[4 * T + 2 * r]), __float_as_uint(kv[4 * T + 2 * r + 1]));
            }
            fence_async_smem();
            __syncwarp();
            if (lane == 0) mbar_arrive(bar(B_KVP));
        }
        PROF_IF(tid == 0, 4);
        uint32_t fq[40];
        {
            float pq[40];
            wg_fence();
#pragma unroll
            for (int kc = 0; kc < 5; kc++) wgmma_rs_n80<1>(pq, qf + 4 * kc, dP + kc * 16, kc != 0);
            wg_commit();
            wg_wait<0>();
            pin_regs<40>(pq);
            if (lane == 0) mbar_arrive(bar(B_PQ));
            uint32_t w0[20], w1[20];
            dual_softmax<false>(pq, w0);
            dual_softmax<false>(pq + 2, w1);
#pragma unroll
            for (int t = 0; t < 20; t++) { fq[2 * t] = w0[t]; fq[2 * t + 1] = w1[t]; }
        }
        PROF_IF(tid == 0, 5);
        {
            int off[7];
#pragma unroll
            for (int u = 0; u < 7; u++) {
                const int idx = min(tid + 256 * u, 1759);
                off[u] = (idx + 2 * (idx / 160)) * 8;
                asm volatile("" : "+r"(off[u]));
            }
            const int hh = (tid >> 1) & 3;
            mbar_wait(bar(B_KVGO), 0);
            PROF_IF(tid == 0, 6); PROF_GT(tid == 0, 2);
            const char* src = reinterpret_cast<const char*>(g_kvsum) + (((lds32(sb + OFF_MISC + 16) >> 4) & 1) * 8 + tj) * KVP_BYTES;
            float2 v[7];
#pragma unroll
            for (int u = 0; u < 7; u++) v[u] = __ldcg(reinterpret_cast<const float2*>(src + off[u]));
#pragma unroll
            for (int u = 0; u < 7; u++) {
                uint32_t x = pack_bf16(v[u].x, v[u].y);
                if (u == 6 && tid >= 64 && (tid & 1)) x = 0x3F803F80u;
                if (u < 6 || tid < 224)
                    sts128(sb + OFF_KVB + (tid + 256 * u) * 16, hh == 0 ? x : 0, hh == 1 ? x : 0, hh == 2 ? x : 0, hh == 3 ? x : 0);
            }
            fence_async_smem();
            bar_sync(1, 256);
        }
        PROF_IF(tid == 0, 7);
        const unsigned epoch = lds32(sb + OFF_MISC + 160 + warp * 4) + 1;
        uint32_t of[4][20];
        {
            float op[44], om[44];
            const uint64_t dK = make_desc(sb + OFF_KVB, 128, 2560, 0);
            wg_fence();
#pragma unroll
            for (int kc = 0; kc < 5; kc++) {
                wgmma_rs_n88<0>(op, fq + 4 * kc, dK + kc * 16, kc != 0);
                wgmma_rs_n88<0>(om, fq + 20 + 4 * kc, dK + 80 + kc * 16, kc != 0);
            }
            wg_commit();
            wg_wait<0>();
            pin_regs<44>(op);
            pin_regs<44>(om);
#pragma unroll
            for (int r = 0; r < 2; r++) {
                const float rp = rcp(op[41 + 2 * r]), rm = rcp(om[41 + 2 * r]);
                const float inv = rcp(fmaf(op[40 + 2 * r], rp, fmaf(om[40 + 2 * r], rm, 1e-6f)));
                const float al = rp * inv, be = rm * inv;
#pragma unroll
                for (int i = 0; i < 10; i++)
                    of[0][2 * i + r] = pack_bf16(fmaf(op[4 * i + 2 * r], al, om[4 * i + 2 * r] * be),
                                                 fmaf(op[4 * i + 2 * r + 1], al, om[4 * i + 2 * r + 1] * be));
            }
#pragma unroll
            for (int j = 0; j < 5; j++) of[0][4 * j] = (of[0][4 * j] & ~1u) | (epoch & 1);
        }
        {
            uint4* const og = g_o + (ti * 64 + warp) * 160 + lane;
            const uint32_t ost = sb + OFF_OUTST + warp * 2560;
#pragma unroll
            for (int j = 0; j < 5; j++) sts128(ost + j * 512 + lane * 16, of[0][4 * j], of[0][4 * j + 1], of[0][4 * j + 2], of[0][4 * j + 3]);
            fence_async_smem();
            __syncwarp();
            const bool leader = elect_one();
            if (leader) {
                bulk_store(og - lane + tj * 1280, ost, 2560);
                bulk_commit();
            }
            PROF_IF(tid == 0, 8);
            auto fetch = [&](int n) {
#pragma unroll
                for (int j = 0; j < 5; j++) ldg128_cg(of[n & 3] + 4 * j, og + ((tj + n) & 7) * 1280 + j * 32);
            };
            float acc[40];
            const uint64_t dB = make_desc(sb + OFF_WO, 2560, 256, 3);
            mbar_wait(bar(B_WO), 0);
            wg_fence();
#pragma unroll
            for (int j = 0; j < 5; j++) wgmma_rs_n80<1>(acc, of[0] + 4 * j, dB + j * 32, j != 0);
            wg_commit();
            if (leader) {
                bulk_wait_read();
                st_relaxed(ohint + tj, epoch);
            }
            __syncwarp();
            PROF_IF(tid == 0, 40);
            for (int it = 0; !__all_sync(0xffffffffu, ld_relaxed(ohint + ((tj + 1 + min(lane, 2)) & 7)) == epoch) && it < (1 << 20); it++) {
            }
            fetch(1);
            PROF_IF(tid == 0, 41);
            fetch(2);
            fetch(3);
            mbar_wait(bar(B_CONV), 0);
#pragma unroll
            for (int n = 1; n < 8; n++) {
                for (int it = 0; __any_sync(0xffffffffu, tag_mismatch(of[n & 3], epoch) & 1) && it < (1 << 20); it++) fetch(n);
                PROF_IF(tid == 0 && n == 1, 42);
                if (n == 6) mbar_wait(bar(B_WOL), 0);
                const uint64_t d = n < 6 ? dB + n * (WO_BYTES >> 4) : make_desc(sb + (n == 6 ? OFF_WO6 : OFF_WPHI), 2560, 256, 3);
                wg_fence();
#pragma unroll
                for (int j = 0; j < 5; j++) wgmma_rs_n80<1>(acc, of[n & 3] + 4 * j, d + j * 32, 1);
                wg_commit();
                PROF_IF(tid == 0 && n == 1, 9); PROF_GT(tid == 0 && n == 1, 3);
                if (n < 5) {
                    wg_wait<1>();
                    fetch(n + 3);
                }
            }
            wg_wait<0>();
            pin_regs<40>(acc);
            PROF_IF(tid == 0, 10);
            const uint32_t a = ost + (lane & 15) * 160 + (lane >> 4) * 16;
#pragma unroll
            for (int t = 0; t < 10; t += 2)
                stsm4(a + t * 16, pack_bf16(acc[4 * t], acc[4 * t + 1]), pack_bf16(acc[4 * t + 2], acc[4 * t + 3]),
                      pack_bf16(acc[4 * t + 4], acc[4 * t + 5]), pack_bf16(acc[4 * t + 6], acc[4 * t + 7]));
            fence_async_smem();
            __syncwarp();
            if (leader) {
                tma_store_2d(&map_out, ost, tj * 80, ti * 128 + warp * 16);
                bulk_commit();
                bulk_wait_read();
            }
            PROF_IF(tid == 0, 11); PROF_GT(tid == 0, 4);
        }
    } else if (warp < 12) {
        const int t = tid - 256, w = warp - 8;
        bar_sync(0, NTHREADS);
        asm volatile("setmaxnreg.inc.sync.aligned.u32 152;");
        const int ch0 = 5 * b;
        const uint32_t work = sb + OFF_WORK;
        {
            const uint32_t workf = work + WK_F;
            const uint32_t krow = (((t >> 3) & 7) * 16 + (t & 7)) * 16;
            const uint32_t tab = work + (t >> 6) * 8192 + krow, tabf = workf + (t >> 6) * 6144 + krow;
            const uint64_t dE = make_desc(work, 128, 2048, 0), dF = make_desc(workf, 128, 2048, 0);
#pragma unroll
            for (int i = 0; i < 4; i++) mbar_wait(bar(B_PAR + i), 0);
            PROF_IF(tid == 256, 38);
#pragma unroll 1
            for (int c = w; c < 5; c += 4) {
                uint32_t m[2];
#pragma unroll
                for (int i = 0; i < 2; i++) {
                    const uint2 x = lds64(sb + OFF_PAR + 2560 * (i + 1) + c * 256 + lane * 8), y = lds64(sb + OFF_PAR + 2560 * (i + 1) + 1280 + c * 256 + lane * 8);
                    const uint32_t v = __vmaxu2(__vmaxu2(x.x & 0x7FFF7FFFu, x.y & 0x7FFF7FFFu), __vmaxu2(y.x & 0x7FFF7FFFu, y.y & 0x7FFF7FFFu));
                    m[i] = __reduce_max_sync(0xffffffffu, max(v >> 16, v & 0xFFFFu)) >> 7;
                }
                const uint32_t ex = min(max((int)(m[0] + m[1]) - 127, 2), 252);
                const float dt = __bfloat162float(__float2bfloat16_rn(expf(lds_bf16(sb + OFF_MISC + 64 + ((10 * b) & 15) + 2 * c))));
                if (lane == 0)
                    sts128(sb + OFF_MISC + 192 + c * 16, __float_as_uint(dt), __float_as_uint(dt * 1.4426950408889634f), (254u - ex) << 23,
                           __float_as_uint(__uint_as_float(ex << 23) * dt));
            }
            for (int i = t; i < (int)(5 * KT_CH / 16); i += 128) sts128(sb + OFF_KT + i * 16, 0, 0, 0, 0);
            bar_sync(4, 128);

            float kh[24];
#pragma unroll
            for (int i = 0; i < 24; i++) kh[i] = 0.f;
#pragma unroll 1
            for (int it = 0; it < (w < 2 ? 7 : 3); it++) {
                const bool priv = it >= 3;
                const int c = priv ? w : 4 - it;
                const uint32_t cs = priv ? 1024 : 2048;
                const uint32_t te = priv ? work + w * 7168 + (krow & 1023) : tab, tf = priv ? te + 4096 : tabf;
                const uint32_t pa = sb + OFF_PAR + c * 256 + (priv ? (it - 3) * 64 + lane * 2 : t * 2);
                const uint4 cst = lds128(sb + OFF_MISC + 192 + c * 16);
                const float omega = __uint_as_float(cst.x) * lds_bf16(pa + 1280), a2 = __uint_as_float(cst.y) * lds_bf16(pa);
                const cplx v1 = cexp_small(a2, -omega, 1.f), v2 = cmul(v1, v1), v4 = cmul(v2, v2), v8 = cmul(v4, v4);
                {
                    const cplx h1 = {v8.r, -v8.i}, h2 = cmul(h1, h1), h3 = cmul(h2, h1), h4 = cmul(h2, h2);
                    const cplx h5 = cmul(h4, h1), h6 = cmul(h4, h2), h7 = cmul(h4, h3), g1 = cmul(h4, h4), g2 = cmul(g1, g1), g3 = cmul(g2, g1);
                    const cplx2h e[4] = {{pack_f16(1.f, h1.r), pack_f16(0.f, h1.i)}, {pack_f16(h2.r, h3.r), pack_f16(h2.i, h3.i)},
                                         {pack_f16(h4.r, h5.r), pack_f16(h4.i, h5.i)}, {pack_f16(h6.r, h7.r), pack_f16(h6.i, h7.i)}};
                    sts128(te, e[0].r, e[1].r, e[2].r, e[3].r);
                    sts128(te + 128, e[0].i, e[1].i, e[2].i, e[3].i);
#pragma unroll
                    for (int je = 1; je < 4; je++) {
                        const uint32_t gg = je == 1 ? pack_f16(g1.r, g1.i) : (je == 2 ? pack_f16(g2.r, g2.i) : pack_f16(g3.r, g3.i));
                        const cplx2h x0 = hmul(e[0], gg), x1 = hmul(e[1], gg), x2 = hmul(e[2], gg), x3 = hmul(e[3], gg);
                        sts128(te + je * cs, x0.r, x1.r, x2.r, x3.r);
                        sts128(te + je * cs + 128, x0.i, x1.i, x2.i, x3.i);
                    }
                }
                {
                    const float down = __uint_as_float(cst.z);
                    const float rh = omega * -0.15915494f;
                    const float rl = fmaf(omega, -6.4206382e-09f, fmaf(omega, -0.15915494f, -rh));
                    const cplx cb = cmul_conj({lds_bf16(pa + 5120), lds_bf16(pa + 6400)}, {lds_bf16(pa + 2560), lds_bf16(pa + 3840)});
                    const cplx vg = cexp_reduced(a2, rh, rl, 256.f), v6 = cmul(v4, v2);
                    const cplx f0 = {cb.r * down, cb.i * down}, f1 = cmul(f0, v1);
                    const cplx2h p01 = {pack_f16(f0.r, f1.r), pack_f16(f0.i, f1.i)};
                    const cplx2h p23 = hmul(p01, pack_f16(v2.r, v2.i)), p45 = hmul(p01, pack_f16(v4.r, v4.i)), p67 = hmul(p01, pack_f16(v6.r, v6.i));
                    sts128(tf, p01.r, p23.r, p45.r, p67.r);
                    sts128(tf + 128, p01.i, p23.i, p45.i, p67.i);
                    const cplx vg2 = cmul(vg, vg), vg3 = cmul(vg2, vg), vg4 = cmul(vg2, vg2), vg6 = cmul(vg4, vg2), vg8 = cmul(vg4, vg4);
                    const cplx2h b04 = lows(p01, p45);
                    const uint32_t mg = pack_f16(vg.r, vg.i);
                    const cplx2h q0 = hmul(lows(p01, p23), mg), q1 = hmul(lows(p45, p67), mg);
                    const cplx2h q2 = hmul(b04, pack_f16(vg2.r, vg2.i)), q3 = hmul(b04, pack_f16(vg3.r, vg3.i));
                    sts128(tf + cs, q0.r, q1.r, q2.r, q3.r);
                    sts128(tf + cs + 128, q0.i, q1.i, q2.i, q3.i);
                    const cplx2h b0g = lows(p01, q0);
                    const cplx2h r0 = hmul(b0g, pack_f16(vg4.r, vg4.i)), r1 = hmul(b0g, pack_f16(vg6.r, vg6.i)), r2 = hmul(b0g, pack_f16(vg8.r, vg8.i));
                    sts128(tf + 2 * cs, r0.r, r1.r, r2.r, 0);
                    sts128(tf + 2 * cs + 128, r0.i, r1.i, r2.i, 0);
                }
                const float up = __uint_as_float(cst.w);
                const uint32_t km = priv ? work + w * 7168 : workf;
                if (!priv) {
                    fence_async_smem();
                    bar_sync(4, 128);
                    PROF_IF(tid == 256 && c == 3, 33);
                    float kc[24];
                    wg_fence();
#pragma unroll
                    for (int ks = 0; ks < 8; ks++) wgmma_ss_f16_n48<1, 1>(kc, dE + ks * 16, dF + ks * 16, ks != 0);
                    wg_commit();
                    wg_wait<0>();
                    pin_regs<24>(kc);
                    PROF_IF(tid == 256 && c == 3, 34);
                    bar_sync(4, 128);
                    const uint32_t slot = km + (w >> 1) * 3072 + ((w & 1) * 16 + g) * 96 + q * 8;
#pragma unroll
                    for (int nt = 0; nt < 3; nt++) {
                        sts64(slot + nt * 32, __float_as_uint(up * (w < 2 ? kc[4 * nt] : kc[12 + 4 * nt])),
                              __float_as_uint(up * (w < 2 ? kc[4 * nt + 1] : kc[12 + 4 * nt + 1])));
                        sts64(slot + nt * 32 + 768, __float_as_uint(up * (w < 2 ? kc[4 * nt + 2] : kc[12 + 4 * nt + 2])),
                              __float_as_uint(up * (w < 2 ? kc[4 * nt + 3] : kc[12 + 4 * nt + 3])));
                    }
                    bar_sync(4, 128);
                } else {
                    __syncwarp();
                    PROF_IF(t == 0, 72 + it);
                    const uint32_t la = km + ((lane >> 3) & 1) * 1024 + ((lane >> 4) * 8 + (lane & 7)) * 16;
                    const uint32_t lb = km + 4096 + (lane >> 4) * 1024 + (lane & 15) * 16;
#pragma unroll
                    for (int ks = 0; ks < 4; ks++) {
                        uint32_t a0[4], a1[4], b0[4], b1[2];
                        ldsm4t(a0, la + ks * 256);
                        ldsm4t(a1, la + 2048 + ks * 256);
                        ldsm4t(b0, lb + ks * 256);
                        ldsm2t(b1, km + 6144 + (lane & 15) * 16 + ks * 256);
                        mma16816_f16(kh, a0, b0[0], b0[1]);
                        mma16816_f16(kh + 4, a0, b0[2], b0[3]);
                        mma16816_f16(kh + 8, a0, b1[0], b1[1]);
                        mma16816_f16(kh + 12, a1, b0[0], b0[1]);
                        mma16816_f16(kh + 16, a1, b0[2], b0[3]);
                        mma16816_f16(kh + 20, a1, b1[0], b1[1]);
                    }
                    __syncwarp();
                    PROF_IF(t == 0 && kh[0] != 1.2345f, 64 + it);
                    if (it < 6) continue;
#pragma unroll
                    for (int i = 0; i < 12; i++)
                        sts64(km + ((i / 6) * 16 + (i & 1) * 8 + g) * 96 + ((i % 6) >> 1) * 32 + q * 8, __float_as_uint(up * kh[2 * i]),
                              __float_as_uint(up * kh[2 * i + 1]));
                    const float dsk = lds_bf16(sb + OFF_MISC + 96 + ((10 * b) & 15) + 2 * c);
                    mbar_wait(bar(B_UDONE), 0);
                    __syncwarp();
                    uint32_t p[11];
#pragma unroll
                    for (int i = 0; i < 6; i++) {
                        const uint4 x = lds128(km + lane * 96 + i * 16);
                        p[2 * i] = pack_bf16(__uint_as_float(x.x) + (i == 0 && lane == 0 ? dsk : 0.f), __uint_as_float(x.y));
                        if (i < 5) p[2 * i + 1] = pack_bf16(__uint_as_float(x.z), __uint_as_float(x.w));
                    }
                    const uint32_t nx = __shfl_sync(0xffffffffu, lane == 0 ? __byte_perm(p[4], p[6], 0x5410) : __byte_perm(p[0], p[4], 0x5410), (lane + 1) & 31);
                    const uint32_t ny = __shfl_sync(0xffffffffu, lane == 0 ? __byte_perm(p[7], p[8], 0x5410) : __byte_perm(p[6], p[7], 0x5410), (lane + 1) & 31);
                    const uint32_t k0 = sb + OFF_KC + c * KC_CH + 32 + lane * 16, k1 = k0 + KC_COPY;
                    sts128(k0, p[0], p[1], p[2], p[3]);
                    sts128(k1, __byte_perm(p[0], p[1], 0x5432), __byte_perm(p[1], p[2], 0x5432), __byte_perm(p[2], p[3], 0x5432),
                           __byte_perm(p[3], nx, 0x5432));
                    const uint32_t a44 = __byte_perm(p[5], 0, 0x1010), n11 = __byte_perm(nx, 0, 0x3232);
                    sts128(k0 + 512, __byte_perm(p[4], 0, 0x1010), __byte_perm(p[4], p[5], 0x5432), a44, __byte_perm(p[5], n11, 0x5432));
                    sts128(k1 + 512, p[4], a44, p[5], n11);
#pragma unroll
                    for (int hf = 0; hf < 2; hf++) {
                        const uint32_t pp = p[6 + hf], nn = __byte_perm(ny, 0, hf ? 0x3232 : 0x1010);
                        const uint32_t b00 = __byte_perm(pp, 0, 0x1010), b44 = __byte_perm(pp, 0, 0x3232);
                        sts128(k0 + 1024 + hf * 512, b00, pp, b44, nn);
                        sts128(k1 + 1024 + hf * 512, b00, b44, __byte_perm(pp, nn, 0x5432), nn);
                    }
                    {
                        const uint32_t aa = __byte_perm(__shfl_sync(0xffffffffu, p[8], 0), 0, 0x1010), k00 = __shfl_sync(0xffffffffu, p[0], 0);
                        const int cp = lane >> 4, k = lane & 15;
                        if (k < 12)
                            sts128(sb + OFF_KC + c * KC_CH + cp * KC_COPY + (k < 2 ? k : 128 + k) * 16, k == 2 ? aa : 0, k == 2 ? aa : 0,
                                   lane == 2 ? aa & 0xFFFFu : 0, lane == 17 ? k00 << 16 : 0);
                    }
                    const uint32_t kt = sb + OFF_KT + c * KT_CH + (lane & 1) * KT_SET;
#pragma unroll
                    for (int kq = 0; kq < 4; kq++) {
                        uint32_t x = (kq & 1) ? p[8 + (kq >> 1)] >> 16 : p[8 + (kq >> 1)];
                        int y = 64 - 16 * kq - (lane >> 1) - (lane & 1);
                        if (kq == 0 && lane == 0) { x = p[10]; y = 0; }
                        sts16(kt + 2 * y, x);
                        if (y > 0) sts16(kt + KT_COPY + 2 * y - 2, x);
                    }
                    PROF_IF(t == 0, 20);
                    break;
                }
                if (lane < 22 && w == 1) {
                    const int cp = lane >= 11, k = lane - cp * 11;
                    if (lane != 12) sts128(sb + OFF_KC + c * KC_CH + cp * KC_COPY + (k < 2 ? k : 129 + k) * 16, 0, 0, 0, 0);
                }
                constexpr uint32_t p2nd = 3072;
                {
                    const int sg = w;
                    const int tt = sg * 32 + lane;
                    const uint32_t row = km + lane * 96;
                    const int col = sg == 0 ? 0 : (sg == 1 ? 8 : 12);
                    const uint4 x0 = lds128(row + col * 4), x1 = lds128(row + p2nd + col * 4);
                    const int ncol = (sg == 0 ? 0 : 4 + 4 * sg - (sg == 3 ? 2 : 0)), wcol = sg == 0 ? 8 : 10 + 2 * sg;
                    const uint32_t na = lane == 31 ? km + wcol * 4 : row + 96 + ncol * 4;
                    const float nx = __uint_as_float(lds32(na)) + __uint_as_float(lds32(na + p2nd));
                    const float s3 = __uint_as_float(lds32(row + 64 + sg * 4)) + __uint_as_float(lds32(row + p2nd + 64 + sg * 4));
                    float v0 = __uint_as_float(x0.x) + __uint_as_float(x1.x);
                    if (tt == 0) v0 += lds_bf16(sb + OFF_MISC + 96 + ((10 * b) & 15) + 2 * c);
                    const uint32_t p0 = pack_bf16(v0, __uint_as_float(x0.y) + __uint_as_float(x1.y));
                    const uint32_t p1 = pack_bf16(__uint_as_float(x0.z) + __uint_as_float(x1.z), __uint_as_float(x0.w) + __uint_as_float(x1.w));
                    const uint32_t nn = pack_bf16(nx, nx);
                    const uint32_t k0 = sb + OFF_KC + c * KC_CH + 32 + tt * 16, k1 = k0 + KC_COPY;
                    if (sg == 0) {
                        const uint4 y0 = lds128(row + 16), y1 = lds128(row + p2nd + 16);
                        const uint32_t p2 = pack_bf16(__uint_as_float(y0.x) + __uint_as_float(y1.x), __uint_as_float(y0.y) + __uint_as_float(y1.y));
                        const uint32_t p3 = pack_bf16(__uint_as_float(y0.z) + __uint_as_float(y1.z), __uint_as_float(y0.w) + __uint_as_float(y1.w));
                        sts128(k0, p0, p1, p2, p3);
                        sts128(k1, __byte_perm(p0, p1, 0x5432), __byte_perm(p1, p2, 0x5432), __byte_perm(p2, p3, 0x5432), __byte_perm(p3, nn, 0x5432));
                    } else if (sg == 1) {
                        const uint32_t a44 = __byte_perm(p1, 0, 0x1010);
                        sts128(k0, __byte_perm(p0, 0, 0x1010), __byte_perm(p0, p1, 0x5432), a44, __byte_perm(p1, nn, 0x5432));
                        sts128(k1, p0, a44, p1, nn);
                    } else {
                        const uint32_t pv = sg == 2 ? p0 : p1;
                        const uint32_t b00 = __byte_perm(pv, 0, 0x1010), b44 = __byte_perm(pv, 0, 0x3232);
                        sts128(k0, b00, pv, b44, nn);
                        sts128(k1, b00, b44, __byte_perm(pv, nn, 0x5432), nn);
                    }
                    uint32_t x3 = pack_bf16(s3, s3);
                    int y3 = 64 - (tt >> 1) - (tt & 1);
                    if (tt == 0) {
                        sts128(k0 + 2048, x3, x3, x3 & 0xFFFFu, 0);
                        sts128(k1 + 2048, x3, x3, 0, 0);
                        sts128(k1 - 16, 0, 0, 0, p0 << 16);
                        x3 = pack_bf16(__uint_as_float(lds32(km + 80)) + __uint_as_float(lds32(km + p2nd + 80)), 0.f);
                        y3 = 0;
                    }
                    const uint32_t kt = sb + OFF_KT + c * KT_CH + (tt & 1) * KT_SET + 2 * y3;
                    sts16(kt, x3);
                    if (y3 > 0) sts16(kt + KT_COPY - 2, x3);
                }
                bar_sync(4, 128);
                PROF_IF(t == 0, 20 - c);
            }
        }

        if (w >= 2 && lane < 16) sts128(work + WK_USM + (w - 2) * USM_CH + (lane >> 3) * USM_PLANE + (lane & 7) * 16, 0, 0, 0, 0);
        __syncwarp();
        mbar_wait(bar(B_USM), 0);
        if (w == 3 && elect_one()) {
            fence_async_global();
            mbar_expect_tx(bar(B_USM + 1), 8192);
#pragma unroll 1
            for (int i = 0; i < 4; i++) bulk_load(work + WK_USM + i * USM_PLANE + USM_PAD, g_ut + (ch0 + 2) * 256 + i * 128, 2048, bar(B_USM + 1));
        }
        PROF_IF(t == 64, 21);
        mbar_wait(bar(B_CNT), 0);
        const uint32_t ul = ((lane >> 3) & 1) * USM_PLANE + USM_PAD + ((lane >> 4) * 8 + (lane & 7)) * 16;
        const uint32_t kl = sb + OFF_KC + ((g & 1) ? 0 : KC_COPY) + ((1 + g + 2 * q) >> 1) * 4;
        PROF_IF(t == 64, 22);
#pragma unroll 1
        for (int own = w < 2; own < 2; own++) {
            const int c = own ? w : 4;
            const uint32_t us = own ? (w < 2 ? sb + OFF_USM + (w + 1) * USM_CH : work + WK_USM + (w - 2) * USM_CH) : sb + OFF_USM;
            const uint32_t ub = ul + us;
            const uint32_t ka = kl + c * KC_CH;
            const uint32_t ka2 = ka + 16 + (blockDim.y - 1);
            float y[64];
#pragma unroll
            for (int i = 0; i < 64; i++) y[i] = 0.f;
            if (own && w >= 2) mbar_wait(bar(B_USM + 1), 0);
            {
            const int lane = fresh_lane(), g = lane >> 2, q = lane & 3;
            if (own || w == 3) {
#pragma unroll
                for (int om = 0; om < 2; om++) {
                    uint32_t bt[16];
#pragma unroll
                    for (int j = 0; j < 4; j++) ldsm4(bt + 4 * j, ub + j * 256 - om * 16);
                    const uint32_t r0 = lds32(ka + 2048 + om * 32), r1 = lds32(ka + 2048 + om * 32 + 16), r2 = lds32(ka2 + 2048 + om * 32),
                                   r3 = lds32(ka + 2048 + om * 32 + 32);
#pragma unroll
                    for (int T = 8; T < 16; T++) mma16816(y + 4 * T, r0, r1, r2, r3, bt[2 * (T - 8)], bt[2 * (T - 8) + 1]);
                }
            }
            {
                const uint32_t rl3 = sb + OFF_KT + ((g & 1) ? 0 : KT_COPY) + ((63 - g + 2 * q) >> 1) * 4;
#pragma unroll 1
                for (int set = own ? 0 : 3 - w; set < (own ? 2 : 4 - w); set++) {
                    const int s0 = g + 2 * q, lo = set ? 5 : 12, hi = set ? 11 : 20;
                    const uint32_t m7 = band_word(s0 - 7, lo, hi), m1 = band_word(s0 + 1, lo, hi), m9 = band_word(s0 + 9, lo, hi),
                                   m17 = band_word(s0 + 17, lo, hi);
                    uint32_t x[9];
                    x[0] = 0;
#pragma unroll
                    for (int j = 0; j < 8; j++) x[j + 1] = lds32(rl3 + c * KT_CH + set * KT_SET - j * 16);
#pragma unroll
                    for (int ks = 0; ks < 4; ks++) {
                        uint32_t b0[4], b1[4], b2[4];
                        ldsm4(b0, ub + ks * 256);
                        ldsm4(b1, ub + ks * 256 - 16);
                        ldsm4(b2, ub + ks * 256 - 32);
                        float d[8];
#pragma unroll
                        for (int j = 0; j < 8; j++) d[j] = 0.f;
#pragma unroll
                        for (int nu = 0; nu < 2; nu++) {
                            mma16816(d + 4 * nu, m1, m9, m9, m17, b1[2 * nu], b1[2 * nu + 1]);
                            mma16816(d + 4 * nu, 0, m7, m7, m1, b0[2 * nu], b0[2 * nu + 1]);
                            mma16816(d + 4 * nu, m17, 0, 0, 0, b2[2 * nu], b2[2 * nu + 1]);
                        }
                        const uint32_t a0 = pack_bf16(d[0], d[1]), a1 = pack_bf16(d[2], d[3]), a2 = pack_bf16(d[4], d[5]), a3 = pack_bf16(d[6], d[7]);
#pragma unroll
                        for (int j = 0; j < 8 - 2 * ks; j++) mma16816(y + 4 * (8 + 2 * ks + j), a0, a1, a2, a3, x[j + 1], x[j]);
                    }
                }
            }
            }
#pragma unroll 1
            for (int om0 = own ? 0 : 2 * (w & 1); om0 < (own ? 4 : 2 * (w & 1) + 2); om0++) {
#pragma unroll
                for (int hf = 0; hf < 2; hf++) {
                    const int om = om0 + 4 * hf;
                    uint32_t bt[32];
#pragma unroll
                    for (int j = 0; j < 8; j++) ldsm4(bt + 4 * j, ub + j * 256 - om * 16);
                    const uint32_t kw = ka + om * 32, kw2 = ka2 + om * 32;
#pragma unroll
                    for (int i = 0; i < 8; i++) {
                        const uint32_t r0 = lds32(kw + i * 256), r1 = lds32(kw + i * 256 + 16), r2 = lds32(kw2 + i * 256), r3 = lds32(kw + i * 256 + 32);
#pragma unroll
                        for (int T = i; T < 16; T++) mma16816(y + 4 * T, r0, r1, r2, r3, bt[2 * (T - i)], bt[2 * (T - i) + 1]);
                    }
                }
            }
            const int lane = fresh_lane(), g = lane >> 2;
            PROF_IF(t == 64, 24 + 2 * own); PROF_IF(t == 0, 28);
            if (!own) {
                const uint32_t xa = work + WK_XCH + lane * 16;
                if (w == 3) {
#pragma unroll
                    for (int j = 0; j < 8; j++)
                        sts128(xa + j * 512, pack_bf16(y[8 * j], y[8 * j + 1]), pack_bf16(y[8 * j + 2], y[8 * j + 3]),
                               pack_bf16(y[8 * j + 4], y[8 * j + 5]), pack_bf16(y[8 * j + 6], y[8 * j + 7]));
                    asm volatile("bar.arrive 7, 64;" ::: "memory");
                    continue;
                }
                bar_sync(7, 64);
#pragma unroll
                for (int j = 0; j < 8; j++) {
                    const uint4 x = lds128(xa + j * 512);
                    const uint32_t xx[4] = {x.x, x.y, x.z, x.w};
#pragma unroll
                    for (int k = 0; k < 4; k++) {
                        y[8 * j + 2 * k] += __uint_as_float(xx[k] << 16);
                        y[8 * j + 2 * k + 1] += __uint_as_float(xx[k] & 0xFFFF0000u);
                    }
                }
            }
            __syncwarp();
            const uint32_t keep = g == 0 ? 0xFFFEFFFEu : 0xFFFFFFFFu, mark = g == 0 ? (~(lds32(sb + OFF_MISC + 32) >> 6) & 1) * 0x00010001u : 0u;
            const uint32_t sa = us + ((lane >> 4) * 8 + (lane & 7)) * 32 + ((lane >> 3) & 1) * 16;
#pragma unroll
            for (int T = 0; T < 16; T += 2) {
                uint32_t x[4];
#pragma unroll
                for (int j = 0; j < 4; j++) x[j] = (pack_bf16(y[4 * T + 2 * j], y[4 * T + 2 * j + 1]) & keep) | mark;
                stsm4t(sa + T * 256, x[0], x[1], x[2], x[3]);
            }
            if (own && lane == 0) mbar_arrive(bar(B_CONV));
            fence_async_smem();
            __syncwarp();
            if (lane == 0) {
                bulk_store(g_yt + (ch0 + c) * 256, us, 4096);
                bulk_commit();
                if (own) {
                    bulk_wait_read();
                    red_inc(g_hint_y + cg * 32);
                }
            }
            PROF_IF(t == 64, 25 + 2 * own); PROF_IF(t == 0, 29);
        }
        __syncwarp();
        const int lane = fresh_lane(), g = lane >> 2, q = lane & 3;
        if (lane == 0) {
            const unsigned target = (lds32(sb + OFF_MISC + 32) & ~63u) + 64;
            for (int it = 0; (int)(ld_relaxed(g_hint_y + cg * 32) - target) < 0 && it < (1 << 20); it++) {}
        }
        __syncwarp();
        PROF_IF(t == 0, 30);
        {
            const uint4* src = g_yt + cg * 80 * 256 + tb * 16 + w * 4 + q;
            const uint32_t tag = ~(lds32(sb + OFF_MISC + 32) >> 6);
            uint32_t r[40];
            int it = 0;
            do {
#pragma unroll
                for (int j = 0; j < 10; j++)
                    ldg128_cg(r + 4 * j, src + (j < 8 ? 32 * (j >> 2) + 8 * (g >> 1) + 2 * (j & 3) + (g & 1) : 64 + 4 * (g >> 1) + 2 * (j & 1) + (g & 1)) * 256);
            } while (__any_sync(0xffffffffu, (tag_mismatch(r, tag) | tag_mismatch(r + 20, tag)) & 1) && ++it < (1 << 20));
            PROF_IF(t == 0, 31);
#pragma unroll
            for (int i = 0; i < 40; i++) asm volatile("movmatrix.sync.aligned.m8n8.trans.b16 %0, %0;" : "+r"(r[i]));
            __nv_bfloat16* orow = prm.out + (size_t)(tb * 128 + w * 32 + 8 * (g >> 1) + (g & 1)) * 1280 + 640 + cg * 80;
#pragma unroll
            for (int j = 0; j < 4; j++) {
                *reinterpret_cast<uint4*>(orow + j * 2560 + 8 * q) = make_uint4(r[j], r[4 + j], r[8 + j], r[12 + j]);
                *reinterpret_cast<uint4*>(orow + j * 2560 + 32 + 8 * q) = make_uint4(r[16 + j], r[20 + j], r[24 + j], r[28 + j]);
                *reinterpret_cast<uint2*>(orow + j * 2560 + 64 + 4 * q) = make_uint2(r[32 + j], r[36 + j]);
            }
        }
        PROF_IF(t == 0, 32);
    } else {
        asm volatile("setmaxnreg.dec.sync.aligned.u32 24;");
        if (warp != 12) {
            if (elect_one()) {
                if (warp == 14) {
                    mbar_init(bar(B_UTILE), 1); mbar_init(bar(B_UDONE), 2); mbar_init(bar(B_CNT), 1);
#pragma unroll
                    for (int c = 0; c < 2; c++) mbar_init(bar(B_USM + c), 1);
                } else if (warp == 13) {
#pragma unroll
                    for (int s = 0; s < 3; s++) mbar_init(bar(B_EMPTY + s), 8);
                    mbar_init(bar(B_WO), 1); mbar_init(bar(B_WOL), 1); mbar_init(bar(B_KVD), 1); mbar_init(bar(B_KVP), 8);
                } else {
                    mbar_init(bar(B_PQ), 8); mbar_init(bar(B_KVGO), 1);
                    mbar_init(bar(B_GATE), 8); mbar_init(bar(B_CONV), 4);
                }
            }
            __syncwarp();
            PROF_IF(lane == 0, warp);
            asm volatile("bar.arrive 5, 128;" ::: "memory");
            bar_sync(0, NTHREADS);
            if (warp == 13 && elect_one()) {
                __nanosleep(300);
                if (UPOS == 0) {
                    mbar_expect_tx(bar(B_UTILE), 20480);
                    tma_load_4d(sb + OFF_USM, &map_u, bar(B_UTILE), cg * 80, 0, tb * 8, 0);
                    tma_load_4d(sb + OFF_USM + 16384, &map_ur, bar(B_UTILE), cg * 80 + 64, 0, tb * 8, 0);
                }
#pragma unroll
                for (int s = 1; s < 3; s++) {
                    mbar_expect_tx(bar(B_FULL + s), STAGE_BYTES);
                    tma_load_2d(sb + s * STAGE_BYTES, &map_x, bar(B_FULL + s), s * 64, ti * 128);
                    tma_load_3d(sb + s * STAGE_BYTES + ST_WM, &map_wm, bar(B_FULL + s), tj * 80, s * 64, 0);
                    tma_load_3d(sb + s * STAGE_BYTES + ST_WR, &map_wr, bar(B_FULL + s), tj * 80 + 64, s * 64, 0);
                    if (s == UPOS) {
                        mbar_expect_tx(bar(B_UTILE), 20480);
                        tma_load_4d(sb + OFF_USM, &map_u, bar(B_UTILE), cg * 80, 0, tb * 8, 0);
                        tma_load_4d(sb + OFF_USM + 16384, &map_ur, bar(B_UTILE), cg * 80 + 64, 0, tb * 8, 0);
                    }
                }
                PROF(50);
            }
            __syncwarp();
        } else {
            bar_sync(0, NTHREADS);
        }
        if (warp == 12) {
            if (elect_one()) {
                int s = 0, ph = 0;
#pragma unroll 1
                for (int kb = 3; kb < 10; kb++) {
                    mbar_wait(bar(B_EMPTY + s), ph);
                    const uint32_t st = sb + s * STAGE_BYTES;
                    mbar_expect_tx(bar(B_FULL + s), STAGE_BYTES);
                    tma_load_2d(st, &map_x, bar(B_FULL + s), kb * 64, ti * 128);
                    tma_load_3d(st + ST_WM, &map_wm, bar(B_FULL + s), tj * 80, kb * 64, 0);
                    tma_load_3d(st + ST_WR, &map_wr, bar(B_FULL + s), tj * 80 + 64, kb * 64, 0);
                    if (++s == 3) { s = 0; ph ^= 1; }
                }
                prefetch_map(&map_wo);
                prefetch_map(&map_out);
                mbar_wait(bar(B_EMPTY + 1), 0);
                mbar_expect_tx(bar(B_WO), 6 * WO_BYTES);
#pragma unroll 1
                for (int n = 0; n < 6; n++) {
                    if (n == 2) mbar_wait(bar(B_EMPTY + 2), 0);
                    tma_load_5d(sb + OFF_WO + n * WO_BYTES, &map_wo, bar(B_WO), 0, 0, ((tj + n) & 7) * 4, 0, tj * 5);
                }
                mbar_expect_tx(bar(B_WOL), 2 * WO_BYTES);
                mbar_wait_long(bar(B_KVD), 0);
                tma_load_5d(sb + OFF_WO6, &map_wo, bar(B_WOL), 0, 0, ((tj + 6) & 7) * 4, 0, tj * 5);
                mbar_wait_long(bar(B_PQ), 0);
                tma_load_5d(sb + OFF_WPHI, &map_wo, bar(B_WOL), 0, 0, ((tj + 7) & 7) * 4, 0, tj * 5);
            }
        } else if (warp < 15) {
            {
                const int hf = warp - 13, r7 = ((lane & 7) >> 1) * 2 + 1 - (lane & 1);
                const int row = (7 - (lane >> 3)) * 16 + hf * 8 + r7;
                uint4* dst = g_ut + (cg * 80 + g) * 256 + tb * 8 + 4 * hf + q;
                mbar_wait_long(bar(B_UTILE), 0);
                PROF_IF(tid == 416, 45);
#pragma unroll kUUnroll
                for (int c8 = 0; c8 < 10; c8++) {
                    const uint32_t src = c8 < 8 ? sb + OFF_USM + row * 128 + ((c8 ^ r7) << 4)
                                                : sb + OFF_USM + 16384 + row * 32 + (((c8 ^ (r7 >> 2)) & 1) << 4);
                    uint32_t r0[4], r1[4];
                    ldsm4t(r0, src);
                    ldsm4t(r1, src - (c8 < 8 ? 64 * 128 : 64 * 32));
                    dst[c8 * 2048] = make_uint4(r0[0], r0[1], r0[2], r0[3]);
                    dst[c8 * 2048 + 128] = make_uint4(r1[0], r1[1], r1[2], r1[3]);
                }
                __syncwarp();
                if (lane == 0) mbar_arrive(bar(B_UDONE));
            }
            if (warp == 13) {
                mbar_wait(bar(B_UDONE), 0);
#pragma unroll
                for (int i = 0; i < 2; i++)
                    if (i * 32 + lane < 48) sts128(sb + OFF_USM + (i * 4 + (lane >> 3)) * USM_PLANE + (lane & 7) * 16, 0, 0, 0, 0);
                __syncwarp();
                if (elect_one()) {
                    PROF(43);
                    mbar_wait(bar(B_CNT), 0);
                    fence_gpu();
                    red_inc(g_cnt_u + cg * 32);
                    wait_counter(g_cnt_u + cg * 32, (lds32(sb + OFF_MISC) & ~15u) + 16);
                    fence_async_global();
                    mbar_expect_tx(bar(B_USM), 12288);
#pragma unroll 1
                    for (int i = 0; i < 6; i++)
                        bulk_load(sb + OFF_USM + i * USM_PLANE + USM_PAD, g_ut + (5 * b + (i < 2 ? 4 : -1)) * 256 + i * 128, 2048, bar(B_USM));
                    PROF(44);
                }
            } else if (elect_one()) {
                mbar_wait(bar(B_CNT), 0);
                const unsigned base = lds32(sb + OFF_MISC + 16) & ~15u;
                const uint32_t par = (base >> 4) & 1;
                mbar_wait_long(bar(B_GATE), 0);
                mbar_wait(bar(B_KVP), 0);
                bulk_reduce_f32(g_kvsum + (par * 8 + tj) * (KVP_BYTES / 4), sb + OFF_KVP, KVP_BYTES);
                bulk_commit();
                bulk_wait_all();
                PROF(46);
                fence_gpu();
                red_inc(g_cnt_kv + tj * 32);
                PROF(47);
                wait_counter(g_cnt_kv + tj * 32, base + 16);
                mbar_arrive(bar(B_KVGO));
                PROF(48);
            }
        } else {
            if (lane < 3) cp_async16(sb + OFF_MISC + lane * 16, lane == 0 ? g_cnt_u + cg * 32 : (lane == 1 ? g_cnt_kv + tj * 32 : g_hint_y + cg * 32));
            if (lane < 8) sts32(sb + OFF_MISC + 160 + lane * 4, ld_relaxed(g_hint_o + (ti * 8 + lane) * 8 + tj));
            asm volatile("cp.async.wait_all;" ::: "memory");
            __syncwarp();
            if (lane == 0) mbar_arrive(bar(B_CNT));
            const unsigned npar = ((lds32(sb + OFF_MISC + 16) >> 4) & 1) ^ 1;
            if (ti == 0) {
                float4* z = reinterpret_cast<float4*>(g_kvsum + (npar * 8 + tj) * (KVP_BYTES / 4));
                for (int i = lane; i < (int)(KVP_BYTES / 16); i += 32) z[i] = make_float4(0.f, 0.f, 0.f, 0.f);
            }
        }
    }
}

typedef CUresult (*EncodeTiledFn)(CUtensorMap*, CUtensorMapDataType, cuuint32_t, void*, const cuuint64_t*, const cuuint64_t*,
                                  const cuuint32_t*, const cuuint32_t*, CUtensorMapInterleave, CUtensorMapSwizzle,
                                  CUtensorMapL2promotion, CUtensorMapFloatOOBfill);

CUtensorMap encode_map(EncodeTiledFn fn, const void* ptr, int rank, const cuuint64_t* dims, const cuuint64_t* strides,
                       const cuuint32_t* box, CUtensorMapSwizzle sw) {
    CUtensorMap m;
    const cuuint32_t es[5] = {1, 1, 1, 1, 1};
    fn(&m, CU_TENSOR_MAP_DATA_TYPE_BFLOAT16, rank, const_cast<void*>(ptr), dims, strides, box, es, CU_TENSOR_MAP_INTERLEAVE_NONE, sw,
       CU_TENSOR_MAP_L2_PROMOTION_L2_128B, CU_TENSOR_MAP_FLOAT_OOB_FILL_NONE);
    return m;
}

}

extern "C" void kernel_launch(void* const* d_in, const int* in_sizes, int n_in, void* d_out, int out_size) {
    (void)in_sizes; (void)n_in; (void)out_size;
    static EncodeTiledFn encode = nullptr;
    if (!encode) {
        cudaDriverEntryPointQueryResult qr;
        cudaGetDriverEntryPoint("cuTensorMapEncodeTiled", reinterpret_cast<void**>(&encode), cudaEnableDefault, &qr);
        cudaFuncSetAttribute(fused_kernel, cudaFuncAttributeMaxDynamicSharedMemorySize, SMEM_BYTES + PROF_SMEM);
    }
    const cuuint64_t dx[2] = {640, 2048}, sx[1] = {1280};
    const cuuint32_t bx[2] = {64, 128};
    const cuuint64_t du[4] = {640, 2, 128, 8}, su[3] = {1280, 16 * 1280, 2 * 1280};
    const cuuint32_t bu[4] = {64, 2, 8, 8}, bur[4] = {16, 2, 8, 8};
    const cuuint64_t dw[3] = {640, 640, 3}, sw[2] = {3840, 1280};
    const cuuint32_t bwm[3] = {64, 64, 3}, bwr[3] = {16, 64, 3};
    const cuuint64_t dwo[5] = {16, 2, 32, 10, 40}, swo[4] = {1280, 20 * 1280, 2 * 1280, 32};
    const cuuint32_t bwo[5] = {16, 2, 4, 10, 5};
    const cuuint64_t dout[2] = {1280, 2048}, sout[1] = {2560};
    const cuuint32_t bout[2] = {80, 16};
    const CUtensorMap map_x = encode_map(encode, d_in[0], 2, dx, sx, bx, CU_TENSOR_MAP_SWIZZLE_128B);
    const CUtensorMap map_wm = encode_map(encode, d_in[1], 3, dw, sw, bwm, CU_TENSOR_MAP_SWIZZLE_128B);
    const CUtensorMap map_wr = encode_map(encode, d_in[1], 3, dw, sw, bwr, CU_TENSOR_MAP_SWIZZLE_32B);
    const CUtensorMap map_wo = encode_map(encode, d_in[3], 5, dwo, swo, bwo, CU_TENSOR_MAP_SWIZZLE_32B);
    const CUtensorMap map_u = encode_map(encode, d_in[4], 4, du, su, bu, CU_TENSOR_MAP_SWIZZLE_128B);
    const CUtensorMap map_ur = encode_map(encode, d_in[4], 4, du, su, bur, CU_TENSOR_MAP_SWIZZLE_32B);
    const CUtensorMap map_out = encode_map(encode, d_out, 2, dout, sout, bout, CU_TENSOR_MAP_SWIZZLE_NONE);
    Params p;
    p.w_phi = static_cast<const __nv_bfloat16*>(d_in[2]);
    for (int i = 0; i < 8; i++) p.ssm[i] = static_cast<const __nv_bfloat16*>(d_in[5 + i]);
    p.out = static_cast<__nv_bfloat16*>(d_out);
    fused_kernel<<<NCTA, NTHREADS, SMEM_BYTES + PROF_SMEM, cudaStreamPerThread>>>(map_x, map_wm, map_wr, map_wo, map_u, map_ur, map_out, p);
}
```
